```python
import torch

def _softmax(x, axis=-1):
    return torch.softmax(x, dim=axis)
def _gelu(x):
    return torch.nn.functional.gelu(x, approximate="tanh")
def _silu(x):
    return torch.nn.functional.silu(x)
def _sigmoid(x):
    return torch.sigmoid(x)
def _layernorm(x, axis=-1, eps=1e-5):
    m = x.mean(dim=axis, keepdim=True)
    v = x.var(dim=axis, keepdim=True, unbiased=False)
    return (x - m) / torch.sqrt(v + eps)
def _scatter_add(tgt, idx, src, axis=0):
    return tgt.clone().index_add_(axis, idx, src)
def _segment_sum(src, seg, n):
    out = torch.zeros((n,) + src.shape[1:], dtype=src.dtype)
    return out.index_add_(0, seg, src)
def _pad(x, pw):
    flat = tuple(v for pair in reversed(pw) for v in pair)
    return torch.nn.functional.pad(x, flat)

kernel_name = 'recurrent_scan__ssm_conv_s5__glu_gated_geglu__prompt'

def setup_inputs():

    _w = (lambda a: (lambda t: t.to(torch.bfloat16) if t.is_floating_point() else t)(torch.as_tensor(a)))
    def _A_setup():
        B, S, D = 1, 2048, 640
        P = D
        Lambda_re = -0.5 * (lambda _x: torch.exp(torch.as_tensor(_x)))((lambda *s: torch.randn(*s, dtype=torch.bfloat16) * 0.8)(P))
        Lambda_im = (lambda *s: torch.randn(*s, dtype=torch.bfloat16) * 0.8)(P) * 1.0
        B_re = (lambda *s: torch.randn(*s, dtype=torch.bfloat16) * 1.6)(P, D) * (D ** -0.5)
        B_im = (lambda *s: torch.randn(*s, dtype=torch.bfloat16) * 1.6)(P, D) * (D ** -0.5)
        C_re = (lambda *s: torch.randn(*s, dtype=torch.bfloat16) * 1.6)(D, P) * (P ** -0.5)
        C_im = (lambda *s: torch.randn(*s, dtype=torch.bfloat16) * 1.6)(D, P) * (P ** -0.5)
        log_dt = (lambda *s: torch.randn(*s, dtype=torch.bfloat16) * 0.8)(P) * 0.3 - 2.0
        Dskip = (lambda *s: torch.randn(*s, dtype=torch.bfloat16) * 0.8)(D)
        return {
            "x": _w((lambda *s: torch.randn(*s, dtype=torch.bfloat16) * 0.05)(B, S, D)),
            "Lambda_re": _w(Lambda_re),
            "Lambda_im": _w(Lambda_im),
            "B_re": _w(B_re),
            "B_im": _w(B_im),
            "C_re": _w(C_re),
            "C_im": _w(C_im),
            "log_dt": _w(log_dt),
            "Dskip": _w(Dskip),
        }
    _A_in = _A_setup()

    def _B_setup():
        B, S, Dm, Df = 1, 2048, 640, 1728
        return {
            "x": _w((lambda *s: torch.randn(*s, dtype=torch.bfloat16) * 0.05)(B, S, Dm)),
            "w_gate": _w((lambda *s: torch.randn(*s, dtype=torch.bfloat16) * 0.2)(Dm, Df) * (Dm ** -0.5)),
            "w_up": _w((lambda *s: torch.randn(*s, dtype=torch.bfloat16) * 0.2)(Dm, Df) * (Dm ** -0.5)),
            "w_down": _w((lambda *s: torch.randn(*s, dtype=torch.bfloat16) * 0.2)(Df, Dm) * (Df ** -0.5)),
        }
    _B_in = _B_setup()

    return {
        "A_x": _A_in["x"],
        "A_Lambda_re": _A_in["Lambda_re"],
        "A_Lambda_im": _A_in["Lambda_im"],
        "A_B_re": _A_in["B_re"],
        "A_B_im": _A_in["B_im"],
        "A_C_re": _A_in["C_re"],
        "A_C_im": _A_in["C_im"],
        "A_log_dt": _A_in["log_dt"],
        "A_Dskip": _A_in["Dskip"],
        "B_x": _B_in["x"],
        "B_w_gate": _B_in["w_gate"],
        "B_w_up": _B_in["w_up"],
        "B_w_down": _B_in["w_down"],
    }

def reference(A_x, A_Lambda_re, A_Lambda_im, A_B_re, A_B_im, A_C_re, A_C_im, A_log_dt, A_Dskip, B_x, B_w_gate, B_w_up, B_w_down):
    def _A_ref(x, Lambda_re, Lambda_im, B_re, B_im, C_re, C_im, log_dt, Dskip):
        Bsz, L, H = x.shape
        Lam = Lambda_re + 1j * Lambda_im
        Bmat = B_re + 1j * B_im
        Cmat = C_re + 1j * C_im
        dt = torch.exp(log_dt)
        Lam_bar = torch.exp(dt * Lam)
        B_bar = ((Lam_bar - 1.0) / Lam)[:, None] * Bmat
        Bu = torch.einsum("bld,pd->blp", x + 0j, B_bar)
        h = torch.zeros_like(Bu[:, 0, :])
        hs = []
        for t in range(L):
            h = Lam_bar[None, :] * h + Bu[:, t, :]
            hs.append(h)
        hseq = torch.stack(hs, 1)
        y = 2.0 * torch.einsum("blp,dp->bld", hseq, Cmat).real + x * Dskip[None, None, :]
        return y

    def _B_ref(x, w_gate, w_up, w_down):
        g = torch.einsum("bsd,df->bsf", x, w_gate)
        u = torch.einsum("bsd,df->bsf", x, w_up)
        h = _gelu(g) * u
        return torch.einsum("bsf,fd->bsd", h, w_down)

    x = A_x
    xn = _layernorm(x, axis=-1)
    s = _A_ref(xn, A_Lambda_re, A_Lambda_im, A_B_re, A_B_im, A_C_re, A_C_im, A_log_dt, A_Dskip)
    g = _silu(_B_ref(xn, B_w_gate, B_w_up, B_w_down))
    return x + s * g
```

```cpp
#include <cuda_runtime.h>
#include <cuda_bf16.h>
#include <cuda.h>
#include <stdint.h>

namespace {

typedef __nv_bfloat16 bf16;

constexpr int SEQ = 2048, DM = 640, DF = 1728;
constexpr int NRB = 16;
constexpr int NCTA = 132;
constexpr int SLAB = 16384;
constexpr int RING1_OFF = 10 * SLAB;
constexpr int ST2 = 36864;
constexpr int NST2 = 6;
constexpr int MISC_OFF = 14 * SLAB;
constexpr int SMEM_BYTES = MISC_OFF + 2176;

constexpr int B_FULL1 = 0;
constexpr int B_RES = 64;
constexpr int B_FULL2 = 144;
constexpr int B_EPOCH = 192;
constexpr int B_STAT = 200;
constexpr int B_DUMMY = 208;
constexpr int B_EMPTY1 = 224;
constexpr int B_DONE = 256;
constexpr int B_INOK = 304;
constexpr int B_SFREE = 320;
constexpr int B_XN = 400;
constexpr int B_EMPTY2 = 408;
constexpr int B_MARK = 456;
constexpr int M_EPOCH = 480;
constexpr int M_RDY = 484;
constexpr int M_NM = 512;
constexpr int M_RS = 1088;
constexpr int M_CS = 1664;

__device__ __align__(1024) float2 g_stats[SEQ];
__device__ __align__(1024) uint4 g_xn[NRB * 10 * 1024];
__device__ __align__(1024) unsigned g_cntX[NRB * 32];
__device__ __align__(1024) uint4 g_hg[NRB * 27 * 1024];
__device__ __align__(1024) uint4 g_hs[NRB * 20 * 1024];
__device__ __align__(1024) uint2 g_agg[NRB * DM];
__device__ __align__(1024) uint4 g_gx[64 * 2 * 10 * 128];
__device__ __align__(1024) uint4 g_cs[8 * 128];
__device__ __align__(1024) unsigned g_flagH[NRB * 40];
__device__ __align__(1024) uint2 g_gb[64 * 2 * 64];
__device__ __align__(1024) unsigned long long g_ticket;

__device__ __forceinline__ uint32_t smem_u32(const void* p) { return (uint32_t)__cvta_generic_to_shared(p); }
__device__ __forceinline__ void mbar_init(uint32_t bar, int cnt) {
  asm volatile("mbarrier.init.shared::cta.b64 [%0], %1;" ::"r"(bar), "r"(cnt) : "memory");
}
__device__ __forceinline__ void mbar_expect_tx(uint32_t bar, uint32_t bytes) {
  asm volatile("mbarrier.arrive.expect_tx.shared::cta.b64 _, [%0], %1;" ::"r"(bar), "r"(bytes) : "memory");
}
__device__ __forceinline__ void mbar_arrive(uint32_t bar) {
  asm volatile("mbarrier.arrive.shared::cta.b64 _, [%0];" ::"r"(bar) : "memory");
}
__device__ __forceinline__ void mbar_arrive_remote(uint32_t cluster_addr) {
  asm volatile("mbarrier.arrive.shared::cluster.b64 _, [%0];" ::"r"(cluster_addr) : "memory");
}
__device__ __forceinline__ void mbar_wait(uint32_t bar, uint32_t parity) {
  asm volatile(
      "{\n.reg .pred p;\n.reg .b32 c;\nmov.b32 c, 16384;\n"
      "LAB_WAIT:\n"
      "mbarrier.try_wait.parity.shared::cta.b64 p, [%0], %1;\n"
      "@p bra LAB_DONE;\n"
      "add.s32 c, c, -1;\nsetp.gt.s32 p, c, 0;\n@p bra LAB_WAIT;\n"
      "LAB_DONE:\n}" ::"r"(bar), "r"(parity) : "memory");
}
__device__ __forceinline__ bool mbar_test(uint32_t bar, uint32_t parity) {
  uint32_t ok;
  asm volatile("{\n.reg .pred p;\nmbarrier.test_wait.parity.shared::cta.b64 p, [%1], %2;\nselp.u32 %0, 1, 0, p;\n}"
               : "=r"(ok) : "r"(bar), "r"(parity) : "memory");
  return ok;
}
__device__ __forceinline__ void mbar_wait_long(uint32_t bar, uint32_t parity) {
#pragma unroll 1
  for (int i = 0; i < 100000 && !mbar_test(bar, parity); i++) __nanosleep(100);
}
__device__ __forceinline__ void mbar_wait_c(uint32_t bar, uint32_t parity, int& budget) {
  asm volatile(
      "{\n.reg .pred p;\n"
      "LAB_WAIT:\n"
      "mbarrier.try_wait.parity.shared::cta.b64 p, [%1], %2;\n"
      "@p bra LAB_DONE;\n"
      "add.s32 %0, %0, -1;\nsetp.gt.s32 p, %0, 0;\n@p bra LAB_WAIT;\n"
      "LAB_DONE:\n}" : "+r"(budget) : "r"(bar), "r"(parity) : "memory");
}
__device__ __forceinline__ void tma_2d(uint32_t dst, const CUtensorMap* tm, uint32_t bar, int c0, int c1) {
  asm volatile(
      "cp.async.bulk.tensor.2d.shared::cluster.global.mbarrier::complete_tx::bytes [%0], [%1, {%3, %4}], [%2];"
      ::"r"(dst), "l"(tm), "r"(bar), "r"(c0), "r"(c1) : "memory");
}
__device__ __forceinline__ void tma_4d(uint32_t dst, const CUtensorMap* tm, uint32_t bar, int c0, int c1, int c2, int c3) {
  asm volatile(
      "cp.async.bulk.tensor.4d.shared::cluster.global.mbarrier::complete_tx::bytes [%0], [%1, {%3, %4, %5, %6}], [%2];"
      ::"r"(dst), "l"(tm), "r"(bar), "r"(c0), "r"(c1), "r"(c2), "r"(c3) : "memory");
}
__device__ __forceinline__ void tma_2d_mc(uint32_t dst, const CUtensorMap* tm, uint32_t bar, int c0, int c1) {
  asm volatile(
      "cp.async.bulk.tensor.2d.shared::cluster.global.mbarrier::complete_tx::bytes.multicast::cluster "
      "[%0], [%1, {%3, %4}], [%2], %5;"
      ::"r"(dst), "l"(tm), "r"(bar), "r"(c0), "r"(c1), "h"((uint16_t)3) : "memory");
}
__device__ __forceinline__ void tma_5d_mc(uint32_t dst, const CUtensorMap* tm, uint32_t bar, int c0, int c3, int c4) {
  asm volatile(
      "cp.async.bulk.tensor.5d.shared::cluster.global.mbarrier::complete_tx::bytes.multicast::cluster "
      "[%0], [%1, {%3, %4, %4, %5, %6}], [%2], %7;"
      ::"r"(dst), "l"(tm), "r"(bar), "r"(c0), "r"(0), "r"(c3), "r"(c4), "h"((uint16_t)3) : "memory");
}
__device__ __forceinline__ void bulk_ld(uint32_t dst, const void* src, uint32_t bytes, uint32_t bar) {
  asm volatile("cp.async.bulk.shared::cluster.global.mbarrier::complete_tx::bytes [%0], [%1], %2, [%3];"
               ::"r"(dst), "l"(src), "r"(bytes), "r"(bar) : "memory");
}
__device__ __forceinline__ void prefetch_tmap(const CUtensorMap* tm) {
  asm volatile("prefetch.tensormap [%0];" ::"l"(tm) : "memory");
}
__device__ __forceinline__ bool elect_one() {
  uint32_t pred;
  asm volatile("{\n.reg .pred P;\nelect.sync _|P, 0xffffffff;\nselp.u32 %0, 1, 0, P;\n}" : "=r"(pred));
  return pred;
}
__device__ __forceinline__ void wgmma_fence() { asm volatile("wgmma.fence.sync.aligned;" ::: "memory"); }
__device__ __forceinline__ void wgmma_commit() { asm volatile("wgmma.commit_group.sync.aligned;" ::: "memory"); }
template <int N>
__device__ __forceinline__ void wgmma_wait() { asm volatile("wgmma.wait_group.sync.aligned %0;" ::"n"(N) : "memory"); }
__device__ __forceinline__ uint64_t make_desc(uint32_t addr, uint32_t lbo, uint32_t sbo, uint32_t swz) {
  uint64_t d = (uint64_t)((addr & 0x3FFFF) >> 4) | ((uint64_t)(lbo >> 4) << 16) | ((uint64_t)(sbo >> 4) << 32) |
               ((uint64_t)swz << 62);
  asm volatile("" : "+l"(d));
  return d;
}
template <int N>
__device__ __forceinline__ void reg_fence(float (&d)[N]) {
#pragma unroll
  for (int i = 0; i < N; i++) asm volatile("" : "+f"(d[i])::"memory");
}
__device__ __forceinline__ unsigned ld_acquire(const unsigned* p) {
  unsigned v;
  asm volatile("ld.acquire.gpu.global.u32 %0, [%1];" : "=r"(v) : "l"(p) : "memory");
  return v;
}
__device__ __forceinline__ void flag_set(unsigned* p, unsigned epoch) {
  asm volatile("fence.acq_rel.gpu;\nst.relaxed.gpu.global.u32 [%0], %1;" ::"l"(p), "r"(epoch) : "memory");
}
__device__ __forceinline__ uint4 ld_relaxed_v4(const uint4* p) {
  uint4 v;
  asm volatile("{\n.reg .b64 a, b;\nld.relaxed.gpu.global.v2.b64 {a, b}, [%4];\nmov.b64 {%0,%1}, a;\nmov.b64 {%2,%3}, b;\n}"
               : "=r"(v.x), "=r"(v.y), "=r"(v.z), "=r"(v.w) : "l"(p) : "memory");
  return v;
}
__device__ __forceinline__ void st_relaxed_v4(uint4* p, uint4 v) {
  asm volatile("{\n.reg .b64 a, b;\nmov.b64 a, {%1,%2};\nmov.b64 b, {%3,%4};\nst.relaxed.gpu.global.v2.b64 [%0], {a, b};\n}"
               ::"l"(p), "r"(v.x), "r"(v.y), "r"(v.z), "r"(v.w) : "memory");
}
__device__ __forceinline__ uint32_t pack_bf16(float lo, float hi) {
  uint32_t r;
  asm("cvt.rn.bf16x2.f32 %0, %1, %2;" : "=r"(r) : "f"(hi), "f"(lo));
  return r;
}
__device__ __forceinline__ uint2 ld_nc_v2(const uint2* p) {
  uint2 v;
  asm volatile("ld.global.nc.v2.u32 {%0,%1}, [%2];" : "=r"(v.x), "=r"(v.y) : "l"(p));
  return v;
}
__device__ __forceinline__ uint4 ld_nc_v4(const uint4* p) {
  uint4 v;
  asm volatile("ld.global.nc.v4.u32 {%0,%1,%2,%3}, [%4];" : "=r"(v.x), "=r"(v.y), "=r"(v.z), "=r"(v.w) : "l"(p));
  return v;
}
__device__ __forceinline__ uint32_t hfma2(uint32_t a, uint32_t b, uint32_t c) {
  uint32_t r;
  asm("fma.rn.bf16x2 %0, %1, %2, %3;" : "=r"(r) : "r"(a), "r"(b), "r"(c));
  return r;
}
__device__ __forceinline__ uint32_t hmul2(uint32_t a, uint32_t b) {
  uint32_t r;
  asm("mul.rn.bf16x2 %0, %1, %2;" : "=r"(r) : "r"(a), "r"(b));
  return r;
}
__device__ __forceinline__ uint32_t hadd2(uint32_t a, uint32_t b) {
  uint32_t r;
  asm("add.rn.bf16x2 %0, %1, %2;" : "=r"(r) : "r"(a), "r"(b));
  return r;
}
__device__ __forceinline__ float bf_lo(uint32_t v) { return __uint_as_float(v << 16); }
__device__ __forceinline__ float bf_hi(uint32_t v) { return __uint_as_float(v & 0xffff0000u); }
__device__ __forceinline__ float round_bf16(float v) { return __bfloat162float(__float2bfloat16_rn(v)); }
__device__ __forceinline__ float tanh_fast(float v) { float r; asm("tanh.approx.f32 %0, %1;" : "=f"(r) : "f"(v)); return r; }
__device__ __forceinline__ float geglu(float g, float u) {
  const float c0 = 0.7978845608028654f, c1 = c0 * 0.044715f;
  float t = tanh_fast(g * fmaf(g * g, c1, c0)), gu = g * u;
  return fmaf(gu, t, gu);
}
__device__ __forceinline__ float silu(float d2) { float h = 0.25f * d2; return fmaf(h, tanh_fast(h), h); }
struct cplx { float r, i; };
__device__ __forceinline__ cplx cmul(cplx a, cplx b) { return {a.r * b.r - a.i * b.i, a.r * b.i + a.i * b.r}; }
__device__ __forceinline__ cplx cfma(cplx a, cplx b, cplx c) {
  return {fmaf(a.r, b.r, fmaf(-a.i, b.i, c.r)), fmaf(a.r, b.i, fmaf(a.i, b.r, c.i))};
}

template <int TA, int TB>
__device__ __forceinline__ void wgmma_n128(float (&d)[64], uint64_t da, uint64_t db, int scale_d) {
  asm volatile(
      "{\n.reg .pred p;\nsetp.ne.b32 p, %66, 0;\n"
      "wgmma.mma_async.sync.aligned.m64n128k16.f32.bf16.bf16 {"
      "%0, %1, %2, %3, %4, %5, %6, %7, %8, %9, %10, %11, %12, %13, %14, %15, %16, %17, %18, %19, %20, %21, %22, %23, "
      "%24, %25, %26, %27, %28, %29, %30, %31, %32, %33, %34, %35, %36, %37, %38, %39, %40, %41, %42, %43, %44, %45, "
      "%46, %47, %48, %49, %50, %51, %52, %53, %54, %55, %56, %57, %58, %59, %60, %61, %62, %63 "
      "}, %64, %65, p, 1, 1, %67, %68;\n}\n"
      :
        "+f"(d[0]), "+f"(d[1]), "+f"(d[2]), "+f"(d[3]), "+f"(d[4]), "+f"(d[5]), "+f"(d[6]), "+f"(d[7]), "+f"(d[8]),
        "+f"(d[9]), "+f"(d[10]), "+f"(d[11]), "+f"(d[12]), "+f"(d[13]), "+f"(d[14]), "+f"(d[15]), "+f"(d[16]),
        "+f"(d[17]), "+f"(d[18]), "+f"(d[19]), "+f"(d[20]), "+f"(d[21]), "+f"(d[22]), "+f"(d[23]), "+f"(d[24]),
        "+f"(d[25]), "+f"(d[26]), "+f"(d[27]), "+f"(d[28]), "+f"(d[29]), "+f"(d[30]), "+f"(d[31]), "+f"(d[32]),
        "+f"(d[33]), "+f"(d[34]), "+f"(d[35]), "+f"(d[36]), "+f"(d[37]), "+f"(d[38]), "+f"(d[39]), "+f"(d[40]),
        "+f"(d[41]), "+f"(d[42]), "+f"(d[43]), "+f"(d[44]), "+f"(d[45]), "+f"(d[46]), "+f"(d[47]), "+f"(d[48]),
        "+f"(d[49]), "+f"(d[50]), "+f"(d[51]), "+f"(d[52]), "+f"(d[53]), "+f"(d[54]), "+f"(d[55]), "+f"(d[56]),
        "+f"(d[57]), "+f"(d[58]), "+f"(d[59]), "+f"(d[60]), "+f"(d[61]), "+f"(d[62]), "+f"(d[63])
      : "l"(da), "l"(db), "r"(scale_d), "n"(TA), "n"(TB));
}

template <int TA, int TB>
__device__ __forceinline__ void wgmma_n160(float (&d)[80], uint64_t da, uint64_t db, int scale_d) {
  asm volatile(
      "{\n.reg .pred p;\nsetp.ne.b32 p, %82, 0;\n"
      "wgmma.mma_async.sync.aligned.m64n160k16.f32.bf16.bf16 {"
      "%0, %1, %2, %3, %4, %5, %6, %7, %8, %9, %10, %11, %12, %13, %14, %15, %16, %17, %18, %19, %20, %21, %22, %23, "
      "%24, %25, %26, %27, %28, %29, %30, %31, %32, %33, %34, %35, %36, %37, %38, %39, %40, %41, %42, %43, %44, %45, "
      "%46, %47, %48, %49, %50, %51, %52, %53, %54, %55, %56, %57, %58, %59, %60, %61, %62, %63, %64, %65, %66, %67, "
      "%68, %69, %70, %71, %72, %73, %74, %75, %76, %77, %78, %79 "
      "}, %80, %81, p, 1, 1, %83, %84;\n}\n"
      :
        "+f"(d[0]), "+f"(d[1]), "+f"(d[2]), "+f"(d[3]), "+f"(d[4]), "+f"(d[5]), "+f"(d[6]), "+f"(d[7]), "+f"(d[8]),
        "+f"(d[9]), "+f"(d[10]), "+f"(d[11]), "+f"(d[12]), "+f"(d[13]), "+f"(d[14]), "+f"(d[15]), "+f"(d[16]),
        "+f"(d[17]), "+f"(d[18]), "+f"(d[19]), "+f"(d[20]), "+f"(d[21]), "+f"(d[22]), "+f"(d[23]), "+f"(d[24]),
        "+f"(d[25]), "+f"(d[26]), "+f"(d[27]), "+f"(d[28]), "+f"(d[29]), "+f"(d[30]), "+f"(d[31]), "+f"(d[32]),
        "+f"(d[33]), "+f"(d[34]), "+f"(d[35]), "+f"(d[36]), "+f"(d[37]), "+f"(d[38]), "+f"(d[39]), "+f"(d[40]),
        "+f"(d[41]), "+f"(d[42]), "+f"(d[43]), "+f"(d[44]), "+f"(d[45]), "+f"(d[46]), "+f"(d[47]), "+f"(d[48]),
        "+f"(d[49]), "+f"(d[50]), "+f"(d[51]), "+f"(d[52]), "+f"(d[53]), "+f"(d[54]), "+f"(d[55]), "+f"(d[56]),
        "+f"(d[57]), "+f"(d[58]), "+f"(d[59]), "+f"(d[60]), "+f"(d[61]), "+f"(d[62]), "+f"(d[63]), "+f"(d[64]),
        "+f"(d[65]), "+f"(d[66]), "+f"(d[67]), "+f"(d[68]), "+f"(d[69]), "+f"(d[70]), "+f"(d[71]), "+f"(d[72]),
        "+f"(d[73]), "+f"(d[74]), "+f"(d[75]), "+f"(d[76]), "+f"(d[77]), "+f"(d[78]), "+f"(d[79])
      : "l"(da), "l"(db), "r"(scale_d), "n"(TA), "n"(TB));
}

#define SAH 2
#define RG 4
#define RS 5
#define BITPOS 2
#define CB 4
#define XSTART 4
#define XPACE 3
#define BLK(i) if ((ones >> (i)) & 1)
struct Params {
  const bf16 *x, *lre, *lim, *logdt, *dskip, *bre, *bim, *cre, *cim, *wg, *wu, *wd;
  float* out;
  unsigned ones;
  unsigned char map[68];
};

#define T5(a, b, c, d, e) ((a) | (b) << 6 | (c) << 12 | (d) << 18 | (e) << 24)
struct Role {
  int role, rb, ct, ntiles;
  unsigned tiles;
  __device__ __forceinline__ int tile(int i) const { return (tiles >> (6 * i)) & 63; }
};
__device__ __forceinline__ Role get_role(const Params& p) {
  unsigned b;
  asm volatile("mov.u32 %0, %%ctaid.x;" : "=r"(b));
  Role r;
  const int cid = p.map[b >> 1];
  r.ct = cid < 64 ? cid & 3 : (cid & 1) * 2 + (b & 1);
  r.role = cid < 64 ? (cid >> 2) & 1 : 2;
  r.rb = cid < 64 ? (cid >> 3) * 2 + (b & 1) : r.ct * 4;
  r.ntiles = r.role == 0 ? 5 : 4;
  r.tiles = r.role == 0 ? (r.ct < 2 ? T5(27, 0, 35, 14, 22) : T5(27, 0, 6, 14, 22)) + r.ct * T5(1, 1, 1, 1, 1)
                        : (r.role == 1 ? T5(31, 4, 10, 18, 0) + r.ct * T5(1, 1, 1, 1, 0) : T5(26, 26, 26, 26, 0));
  return r;
}

template <int TB, int A_RING, int WAIT_RES, int HAND, class F>
__device__ __forceinline__ void mainloop1(float (&acc)[2][64], uint32_t sbase, int tile, int wg, bool hand_en,
                                          int next_bar, int next_cnt, int lane, F shadow) {
  const int side = tile & 1;
  const uint32_t misc = sbase + MISC_OFF;
  constexpr int BS = TB ? 128 : 2, KS = SLAB >> 4;
  uint64_t ds = make_desc(sbase, (TB && A_RING) ? 8192 : 16, 1024, 1);
  uint64_t dr = make_desc(sbase + RING1_OFF + side * 2 * SLAB, (TB && !A_RING) ? 8192 : 16, 1024, 1);
  uint64_t dr2 = make_desc(sbase + RING1_OFF + (side ^ 1) * 2 * SLAB, (TB && !A_RING) ? 8192 : 16, 1024, 1);
  uint32_t fb = misc + B_FULL1 + side * 32, rbar = misc + B_RES;
  constexpr bool PAIR = !(TB && A_RING);
  uint32_t rm = misc;
  if (PAIR) asm volatile("mapa.shared::cluster.u32 %0, %1, %2;" : "=r"(rm) : "r"(misc), "r"(lane & 1));
  uint32_t e0 = rm + B_EMPTY1 + side * 16, e1 = rm + B_DUMMY;
  const bool hon = hand_en && (HAND == 2 || lane == 0);
  uint32_t h0 = rm + B_DUMMY, h1 = hon ? (HAND == 2 ? rm + B_EMPTY2 : misc + B_SFREE) : h0;
  const uint32_t hs = hon ? 8 : 0;
  uint32_t l0 = lane < (PAIR ? 2 : 1);
  asm volatile("" : "+r"(l0));
  int budget = 32768;
  if (tile) asm volatile("bar.sync %0, 256;" ::"r"(1 + wg) : "memory");
  uint32_t pa = (tile >> 1) & 1, pb = 0;
  const uint32_t ea = e0, eb = e0 ^ 16;
  auto kblock = [&](int j, int first) {
    mbar_wait_c(fb + j * 8, j < 2 ? pa : pb, budget);
    if (WAIT_RES && tile < 2) mbar_wait_c(rbar + j * 8, tile & 1, budget);
    const uint64_t r = (j < 2 ? dr : dr2) + (j & 1) * KS, x = ds + j * KS;
    const uint64_t da = A_RING ? r : x, db = A_RING ? x : r;
    wgmma_fence();
#pragma unroll
    for (int kk = 0; kk < 4; kk++) {
      wgmma_n128<0, TB>(acc[0], da + kk * 2, db + kk * BS, kk ? 1 : first);
      wgmma_n128<0, TB>(acc[1], da + 512 + kk * 2, db + kk * BS, kk ? 1 : first);
    }
    wgmma_commit();
    wgmma_wait<1>();
    if (l0) {
      mbar_arrive_remote(j == 0 ? e1 : (j == 3 ? eb : ea + (j - 1) * 8));
      if (HAND == 1 || (HAND == 2 && (j & 1))) mbar_arrive_remote(h0);
    }
    if (HAND == 1 || (HAND == 2 && (j & 1))) { h0 = h1; h1 += hs; }
  };
#pragma unroll 1
  for (int i = 0;; i++) {
    asm volatile("" : "+l"(dr), "+l"(dr2));
    kblock(0, i);
    kblock(1, 1);
    if (i == 2) break;
    kblock(2, 1);
    kblock(3, 1);
    ds += 4 * KS; rbar += 32; pa ^= 1; pb ^= 1; e1 = eb + 8;
  }
  e1 = ea + 8;
  if (next_bar) asm volatile("bar.arrive %0, %1;" ::"r"(next_bar), "r"(next_cnt) : "memory");
  shadow();
  wgmma_wait<0>();
  reg_fence(acc[0]);
  reg_fence(acc[1]);
  if (l0) {
    mbar_arrive_remote(e1);
    if (HAND == 1) mbar_arrive_remote(h0);
  }
}

template <int ISG, int R>
__device__ __forceinline__ void mainloop2(float (&acc)[80], uint32_t sbase, int wg, int lane) {
  constexpr int NK = ISG ? 27 : 20, NS = NST2 - 1, NREL = NK - NS;
  constexpr int AS = ISG ? 2 : 128;
  static_assert(NK - R >= NREL, "");
  const uint32_t misc = sbase + MISC_OFF;
  const uint64_t da0 = make_desc(sbase + wg * 8192, 16, 1024, 1);
  const uint64_t db0 = ISG ? make_desc(sbase + SLAB, 2048, 512, 2) : make_desc(sbase + SLAB, 16, 1024, 1);
  uint32_t emp;
  asm volatile("mapa.shared::cluster.u32 %0, %1, %2;" : "=r"(emp) : "r"(misc + B_EMPTY2), "r"(lane & 1));
  const bool l01 = lane < 2;
  uint64_t da = da0, db = db0;
  uint32_t so = 0, par = 0, prev = emp;
  int budget = 32768;
  auto step = [&](int it) {
    mbar_wait_c(misc + B_FULL2 + so, par, budget);
    wgmma_fence();
#pragma unroll
    for (int kk = 0; kk < 4; kk++)
      wgmma_n160<!ISG, ISG>(acc, da + kk * AS, db + (ISG ? (kk & 1) * 64 + (kk >> 1) * 640 : kk * 2), kk ? 1 : it);
    wgmma_commit();
  };
  auto next = [&] {
    so += 8; da += ST2 >> 4; db += ST2 >> 4;
    if (so == NS * 8) { so = 0; par ^= 1; da = da0; db = db0; }
  };
  auto body = [&](int it) {
    step(it);
    wgmma_wait<1>();
    if (l01 && (unsigned)(it - 1) < (unsigned)NREL) mbar_arrive_remote(prev);
    prev = emp + so;
    next();
  };
  {
    constexpr int NU = (NREL + 1 < NK - R ? NREL + 1 : NK - R) / NS * NS;
    uint32_t l01r = l01;
    asm volatile("" : "+r"(l01r));
    prev = emp - B_EMPTY2 + B_DUMMY;
    mbar_wait_c(misc + B_FULL2, 0, budget);
    asm volatile("bar.sync 4, 384;" ::"l"(da), "l"(db), "r"(prev), "r"(l01r) : "memory");
#pragma unroll 1
    for (int r = 0; r < NU / NS; r++) {
      asm volatile("" : "+l"(da), "+l"(db));
#pragma unroll
      for (int sl = 0; sl < NS; sl++) {
        mbar_wait_c(misc + B_FULL2 + sl * 8, par, budget);
        wgmma_fence();
#pragma unroll
        for (int kk = 0; kk < 4; kk++)
          wgmma_n160<!ISG, ISG>(acc, da + sl * (ST2 >> 4) + kk * AS, db + sl * (ST2 >> 4) + (ISG ? (kk & 1) * 64 + (kk >> 1) * 640 : kk * 2),
                                (kk | sl) ? 1 : r);
        wgmma_commit();
        wgmma_wait<1>();
        if (l01r) mbar_arrive_remote(sl ? emp + (sl - 1) * 8 : prev);
      }
      par ^= 1;
      prev = emp + (NS - 1) * 8;
    }
#pragma unroll 1
    for (int it = NU; it < NK - R; it++) body(it);
  }
  if (wg != ISG) {
    if (NK - R == NREL) { wgmma_wait<0>(); if (l01) mbar_arrive_remote(prev); }
    asm volatile("bar.sync 5, 256;" ::: "memory");
  }
#pragma unroll 1
  for (int it = NK - R; it < NK; it++) {
    step(1);
    if (NK - R == NREL && it == NK - R && wg == ISG) { wgmma_wait<1>(); if (l01) mbar_arrive_remote(prev); }
    next();
  }
  if (wg == ISG) {
    wgmma_wait<1>();
    asm volatile("bar.arrive 5, 256;" ::: "memory");
  }
}

__device__ __forceinline__ float lds_f32(uint32_t a) {
  float v;
  asm volatile("ld.shared.f32 %0, [%1];" : "=f"(v) : "r"(a) : "memory");
  return v;
}

__device__ __forceinline__ void lds_v4(float* v, uint32_t a) {
  asm volatile("ld.shared.v4.f32 {%0,%1,%2,%3}, [%4];" : "=f"(v[0]), "=f"(v[1]), "=f"(v[2]), "=f"(v[3]) : "r"(a) : "memory");
}

__device__ __forceinline__ uint32_t glu_dst(int tile_index, int w, int lane) {
  const int g = lane >> 2, m0 = 32 * (w >> 1) + 8 * (g >> 1) + 4 * (w & 1) + (g & 1);
  uint32_t o = tile_index * 1024 + m0 * 8 + ((lane & 3) ^ (m0 & 7));
  asm volatile("" : "+r"(o));
  return o;
}
__device__ __forceinline__ void epilogue_glu(float (&acc)[2][64], uint32_t o0, unsigned ones) {
#pragma unroll
  for (int half = 0; half < 2; half++)
#pragma unroll
    for (int jh = 0; jh < 2; jh++) {
      uint4* dst = g_hg + (o0 ^ (4 * jh + 2 * half)) + 16 * half;
#pragma unroll
      for (int mt = 0; mt < 2; mt++) BLK(mt * 4 + half * 2 + jh) {
        uint32_t v[4];
#pragma unroll
        for (int jl = 0; jl < 4; jl++) {
          const int a = 4 * (4 * jh + jl) + 2 * half;
          v[jl] = pack_bf16(geglu(acc[mt][a], acc[mt][32 + a]), geglu(acc[mt][a + 1], acc[mt][33 + a]));
        }
        dst[512 * mt] = make_uint4(v[0], v[1], v[2], v[3]);
      }
    }
}

__device__ __forceinline__ cplx lam_bar(float lr, float li, float ldt) {
  float dt = round_bf16(expf(ldt));
  float mag = expf(dt * lr), sn, cs;
  sincosf(dt * li, &sn, &cs);
  return {mag * cs, mag * sn};
}

__device__ __forceinline__ void epilogue_ssm(float (&acc)[2][64], cplx lamq, cplx cq, int rb, int grp, int w, int lane,
                                             unsigned epoch, unsigned ones, uint32_t misc, bool fold) {
  const int g = lane >> 2, q = lane & 3;
  if (fold) {
    float cs[2][2];
#pragma unroll
    for (int c = 0; c < 2; c++) {
      cs[0][c] = lds_f32(misc + M_CS + (16 * w + 8 * c + g) * 4);
      cs[1][c] = lds_f32(misc + M_CS + (64 + 16 * w + 8 * c + g) * 4);
    }
#pragma unroll
    for (int j2 = 0; j2 < 8; j2++) {
      float r[4], m[4];
      lds_v4(r, misc + M_RS + q * 144 + j2 * 16);
      lds_v4(m, misc + M_NM + q * 144 + j2 * 16);
#pragma unroll
      for (int i = 0; i < 4; i++)
#pragma unroll
        for (int c = 0; c < 2; c++) {
          int a = 8 * j2 + 4 * (i >> 1) + 2 * c + (i & 1);
          acc[0][a] = fmaf(m[i], cs[0][c], acc[0][a]) * r[i];
          acc[1][a] = fmaf(m[i], cs[1][c], acc[1][a]) * r[i];
        }
    }
  }
  const unsigned par = epoch & 1;
  auto lam_of = [&](int c) { return cplx{__shfl_sync(~0u, lamq.r, c, 4), __shfl_sync(~0u, lamq.i, c, 4)}; };
  auto pow32 = [&](cplx t) {
#pragma unroll
    for (int i = 0; i < 5; i++) t = cmul(t, t);
    return t;
  };
  cplx h[2];
#pragma unroll
  for (int c = 0; c < 2; c++) {
    const cplx lam = lam_of(c);
    cplx s = {acc[0][2 * c], acc[1][2 * c]};
#pragma unroll
    for (int j = 1; j < 32; j++) {
      const int a = 4 * (j >> 1) + 2 * c + (j & 1);
      s = cfma(lam, s, cplx{acc[0][a], acc[1][a]});
    }
    const cplx t = pow32(lam);
    cplx v = {__shfl_up_sync(~0u, s.r, 1, 4), __shfl_up_sync(~0u, s.i, 1, 4)};
    if (q >= 1) s = cfma(t, v, s);
    v = {__shfl_up_sync(~0u, s.r, 2, 4), __shfl_up_sync(~0u, s.i, 2, 4)};
    if (q >= 2) s = cfma(cmul(t, t), v, s);
    if (q == 3 && rb < NRB - 1)
      asm volatile("{\n.reg .b64 a;\nmov.b64 a, {%1,%2};\nst.relaxed.gpu.global.b64 [%0], a;\n}" ::"l"(
                       g_agg + rb * DM + grp * 64 + 16 * w + 8 * c + g), "r"((__float_as_uint(s.r) & ~1u) | par), "f"(s.i) : "memory");
    h[c] = {__shfl_up_sync(~0u, s.r, 1, 4), __shfl_up_sync(~0u, s.i, 1, 4)};
    if (q == 0) h[c] = {0.f, 0.f};
  }
  {
    const cplx cf[2] = {{__shfl_sync(~0u, cq.r, 0, 4), __shfl_sync(~0u, cq.i, 0, 4)}, {__shfl_sync(~0u, cq.r, 1, 4), __shfl_sync(~0u, cq.i, 1, 4)}};
#pragma unroll
    for (int b = 0; b < 64 / CB; b++) BLK(b & 15) {
#pragma unroll
      for (int k = CB * b; k < CB * b + CB; k++) {
        const cplx u = cmul(cf[(k >> 1) & 1], cplx{acc[0][k], acc[1][k]});
        acc[0][k] = u.r; acc[1][k] = u.i;
      }
    }
  }
  {
    int ln = lane;
    asm volatile("" : "+r"(ln));
    const int jb0 = rb - 1 - 4 * (ln & 3);
    const uint2* ap = g_agg + jb0 * DM + grp * 64 + 16 * w + (ln >> 2);
    uint2 a[2][4];
#pragma unroll
    for (int c = 0; c < 2; c++)
#pragma unroll
      for (int i = 0; i < 4; i++) a[c][i] = make_uint2(jb0 - i < 0 ? par : par ^ 1, 0);
#pragma unroll 1
    for (int tries = 0; tries < 20000; tries++) {
      unsigned bad = 0;
#pragma unroll
      for (int c = 0; c < 2; c++)
#pragma unroll
        for (int i = 0; i < 4; i++) {
          const unsigned b = (a[c][i].x ^ par) & 1;
          asm volatile("{\n.reg .pred p;\n.reg .b64 a;\nsetp.ne.u32 p, %3, 0;\nmov.b64 a, {%0,%1};\n"
                       "@p ld.relaxed.gpu.global.b64 a, [%2];\nmov.b64 {%0,%1}, a;\n}"
                       : "+r"(a[c][i].x), "+r"(a[c][i].y) : "l"(ap - i * DM + 8 * c), "r"(b) : "memory");
          bad |= b;
        }
      if (__all_sync(~0u, bad == 0)) break;
    }
#pragma unroll
    for (int c = 0; c < 2; c++) {
      const cplx l32 = pow32(lam_of(c)), l64 = cmul(l32, l32);
      cplx pw = cmul(l64, l64), t = {__uint_as_float(a[c][3].x & ~1u), __uint_as_float(a[c][3].y)};
#pragma unroll
      for (int i = 2; i >= 0; i--) t = cfma(pw, t, cplx{__uint_as_float(a[c][i].x & ~1u), __uint_as_float(a[c][i].y)});
      pw = cmul(pw, pw); pw = cmul(pw, pw);
      if (q & 1) t = cmul(t, pw);
      if (q & 2) t = cmul(t, cmul(pw, pw));
      t.r += __shfl_xor_sync(~0u, t.r, 1); t.i += __shfl_xor_sync(~0u, t.i, 1);
      t.r += __shfl_xor_sync(~0u, t.r, 2); t.i += __shfl_xor_sync(~0u, t.i, 2);
      if (q & 1) t = cmul(t, l32);
      if (q & 2) t = cmul(t, l64);
      h[c] = cmul(cplx{__shfl_sync(~0u, cq.r, c, 4), __shfl_sync(~0u, cq.i, c, 4)}, cplx{t.r + h[c].r, t.i + h[c].i});
    }
  }
  asm volatile("" : "+r"(lane));
  uint4* tre = g_hs + (size_t)(rb * 20 + 2 * grp) * 1024 + (16 * w + (lane >> 2)) * 8;
  const int sw = (lane & 3) ^ (lane >> 2);
  mbar_wait_long(misc + B_DONE + (fold ? 8 : 24), 0);
  const cplx lam[2] = {lam_of(0), lam_of(1)};
#pragma unroll
  for (int i = 0; i < 4; i++)
#pragma unroll
    for (int c = 0; c < 2; c++) BLK(2 * i + c) {
      uint32_t vr[4], vi[4];
#pragma unroll
      for (int jl = 0; jl < 4; jl++) {
        const int k = 4 * (4 * i + jl) + 2 * c;
        const cplx s0 = cfma(lam[c], h[c], cplx{acc[0][k], acc[1][k]});
        h[c] = cfma(lam[c], s0, cplx{acc[0][k + 1], acc[1][k + 1]});
        vr[jl] = pack_bf16(s0.r, h[c].r);
        vi[jl] = pack_bf16(-s0.i, -h[c].i);
      }
      const int off = (i >> 1) * 512 + 64 * c + (sw ^ (4 * (i & 1)));
      tre[off] = make_uint4(vr[0], vr[1], vr[2], vr[3]);
      tre[1024 + off] = make_uint4(vi[0], vi[1], vi[2], vi[3]);
    }
}

struct NormK { uint32_t nm, rh, rl; };
__device__ __forceinline__ NormK norm_consts(float mean, float rs) {
  NormK k;
  k.nm = pack_bf16(-mean, -mean);
  k.rh = pack_bf16(rs, rs);
  float lo = rs - bf_lo(k.rh);
  k.rl = pack_bf16(lo, lo);
  return k;
}
__device__ __forceinline__ uint32_t norm2(uint32_t x, const NormK& k) {
  uint32_t c = hadd2(x, k.nm);
  return hfma2(c, k.rh, hmul2(c, k.rl));
}
__device__ __forceinline__ unsigned get_epoch(uint32_t misc) {
  mbar_wait(misc + B_EPOCH, 0);
  unsigned e;
  asm volatile("ld.shared.u32 %0, [%1];" : "=r"(e) : "r"(misc + M_EPOCH) : "memory");
  return e;
}

__device__ __forceinline__ unsigned poll_ready(int role, int rb, int lane, unsigned epoch) {
  return __ballot_sync(~0u, ld_acquire(g_flagH + rb * 40 + (role ? min(lane, 26) : 27 + min(lane >> 1, 9))) == epoch);
}
__device__ __forceinline__ void wait_xn(int rb, unsigned epoch) {
#pragma unroll 1
  for (int tries = 0; tries < 20000; tries++)
    if (ld_acquire(g_cntX + rb * 32) == epoch * 8) break;
  asm volatile("fence.proxy.async.global;" ::: "memory");
}
__device__ __forceinline__ void prefetch_l2(const void* p) { asm volatile("prefetch.global.L2 [%0];" ::"l"(p)); }
__device__ __forceinline__ void prefetch_tile(const Params& p, int id, int rb, int lane) {
  if (rb >= 10) return;
  const bool glu = id < 27;
  const size_t pitch = glu ? DF : DM, o = glu ? (size_t)(rb * 64 + lane) * DF + id * 64 : (size_t)((id - 27) * 64 + lane) * DM + rb * 64;
  const bf16 *a = (glu ? p.wg : p.bre) + o, *b = (glu ? p.wu : p.bim) + o;
  prefetch_l2(a); prefetch_l2(a + 32 * pitch); prefetch_l2(b); prefetch_l2(b + 32 * pitch);
}
__device__ __forceinline__ uint32_t ld_u16(const bf16* p) {
  uint16_t v;
  asm volatile("ld.global.nc.u16 %0, [%1];" : "=h"(v) : "l"(p));
  return v;
}
__device__ __forceinline__ void cluster_arrive() { asm volatile("barrier.cluster.arrive.relaxed.aligned;" ::: "memory"); }
__device__ __forceinline__ void cluster_wait() { asm volatile("barrier.cluster.wait.aligned;" ::: "memory"); }

__global__ void __cluster_dims__(2, 1, 1) __launch_bounds__(512, 1)
fused_kernel(const __grid_constant__ CUtensorMap tm_x, const __grid_constant__ CUtensorMap tm_bre,
             const __grid_constant__ CUtensorMap tm_bim, const __grid_constant__ CUtensorMap tm_wg,
             const __grid_constant__ CUtensorMap tm_wu, const __grid_constant__ CUtensorMap tm_xo,
             const __grid_constant__ CUtensorMap tm_wd, const __grid_constant__ CUtensorMap tm_cre,
             const __grid_constant__ CUtensorMap tm_cim,
             const __grid_constant__ CUtensorMap tm_out, const Params p) {
  extern __shared__ __align__(1024) uint8_t smem_raw[];
  uint32_t sbase = smem_u32(smem_raw);
  asm volatile("mov.u32 %0, %0;" : "+r"(sbase));
  const uint32_t misc = sbase + MISC_OFF, ring = sbase + RING1_OFF;
  const int warp = __shfl_sync(~0u, threadIdx.x >> 5, 0), lane = threadIdx.x & 31;
  if (warp >= 12) {
    const Role R = get_role(p);
    const int role = R.role, rb = R.rb, ct = R.ct, ntiles = R.ntiles, rank = blockIdx.x & 1;
    if (elect_one()) {
      if (warp == 12) {
        for (int i = 0; i < 8; i++) mbar_init(misc + B_FULL1 + i * 8, 1);
        for (int i = 0; i < 10; i++) mbar_init(misc + B_RES + i * 8, 1);
      } else if (warp == 13) {
        for (int i = 0; i < 7; i++) mbar_init(misc + B_FULL2 + i * 8, 1);
        mbar_init(misc + B_STAT, 2);
        mbar_init(misc + B_DUMMY, 1);
        mbar_init(misc + B_MARK, 1);
        for (int i = 0; i < NST2; i++) mbar_init(misc + B_EMPTY2 + i * 8, 16);
      } else if (warp == 14) {
        prefetch_tmap(&tm_x); prefetch_tmap(rank ? &tm_bim : &tm_bre);
        for (int i = 0; i < 10; i++) mbar_init(misc + B_SFREE + i * 8, 4);
        mbar_init(misc + B_XN, 8);
        asm volatile("st.shared.u32 [%0], %1;" ::"r"(misc + M_RDY), "r"(0) : "memory");
      } else {
        for (int i = 0; i < 4; i++) mbar_init(misc + B_EMPTY1 + i * 8, role == 2 ? 4 : 8);
        for (int i = 0; i < 6; i++) mbar_init(misc + B_DONE + i * 8, 4);
        mbar_init(misc + B_INOK, 4);
      }
      asm volatile("fence.mbarrier_init.release.cluster;" ::: "memory");
    }
    __syncwarp();
    cluster_arrive();
    asm volatile("setmaxnreg.dec.sync.aligned.u32 32;");
    if (warp == 12) {
      int budget = 65536;
      if (role != 2) {
        {
          const int r0 = (R.tile(0) - 27) * 64;
#pragma unroll 1
          for (int kb = 0; kb < 10; kb++) {
            const uint32_t slot = ring + (kb & 3) * SLAB, bar = misc + B_FULL1 + (kb & 3) * 8, rbar = misc + B_RES + kb * 8;
            if (kb >= 4) mbar_wait_c(misc + B_EMPTY1 + (kb & 3) * 8, (kb >> 3) & 1, budget);
            if (kb < 4 && elect_one()) {
              mbar_expect_tx(rbar, SLAB);
              tma_4d(sbase + kb * SLAB, &tm_x, rbar, kb * 64, 0, rb * 4, 0);
            }
            if (kb == 0) cluster_wait();
            if (elect_one()) {
              mbar_expect_tx(bar, SLAB);
              tma_2d_mc(slot + rank * 8192, rank ? &tm_bim : &tm_bre, bar, kb * 64, r0);
            }
            if (kb >= 3) {
#pragma unroll 1
              for (int k = kb == 3 ? 4 : kb + SAH; k <= kb + SAH && k < 10; k++)
                if (elect_one()) {
                  mbar_expect_tx(misc + B_RES + k * 8, SLAB);
                  tma_4d(sbase + k * SLAB, &tm_x, misc + B_RES + k * 8, k * 64, 0, rb * 4, 0);
                }
            }
          }
        }
        uint32_t pr = 5;
#pragma unroll 1
        for (int tile = 1; tile < ntiles; tile++) {
          const int id = R.tile(tile);
          const bool glu = id < 27;
          const CUtensorMap* ma = glu ? (rank ? &tm_wu : &tm_wg) : (rank ? &tm_bim : &tm_bre);
          int x0 = glu ? id * 64 : 0, x1 = glu ? 0 : (id - 27) * 64;
          const int e0 = glu ? 0 : 64, e1 = glu ? 64 : 0;
          uint32_t fb = misc + B_FULL1 + (tile & 1) * 32;
#pragma unroll 1
          for (int i = 0; i < 5; i++, pr++) {
            const uint32_t slot = ring + rank * 8192 + (pr & 1) * 2 * SLAB, eb = misc + B_EMPTY1 + (pr & 1) * 16, par = (~pr >> 1) & 1;
#pragma unroll
            for (int h = 0; h < 2; h++) {
              mbar_wait_c(eb + h * 8, par, budget);
              if (elect_one()) {
                mbar_expect_tx(fb + h * 8, SLAB);
                tma_2d_mc(slot + h * SLAB, ma, fb + h * 8, x0, x1);
              }
              x0 += e0; x1 += e1;
            }
            fb ^= 16;
          }
        }
      } else {
        cluster_wait();
        const unsigned epoch = get_epoch(misc);
#pragma unroll 1
        for (int i = 0; i < 4; i++) wait_xn(rb + i, epoch);
#pragma unroll 1
        for (int kb = 0; kb < 10; kb++)
          if (elect_one()) {
            mbar_expect_tx(misc + B_RES + kb * 8, SLAB);
            tma_2d(sbase + kb * SLAB, &tm_wg, misc + B_RES + kb * 8, 26 * 64, kb * 64);
            tma_2d(sbase + kb * SLAB + 8192, &tm_wu, misc + B_RES + kb * 8, 26 * 64, kb * 64);
          }
        uint32_t fb = misc + B_FULL1, k5 = 0;
#pragma unroll 1
        for (uint32_t pr = 0; pr < 20; pr++) {
          const uint32_t slot = ring + (pr & 1) * 2 * SLAB, eb = misc + B_EMPTY1 + (pr & 1) * 16, par = (~pr >> 1) & 1;
#pragma unroll
          for (int h = 0; h < 2; h++) {
            mbar_wait_c(eb + h * 8, par, budget);
            if (elect_one()) {
              mbar_expect_tx(fb + h * 8, SLAB);
              bulk_ld(slot + h * SLAB, g_xn + (rb * 10 + 2 * pr + h) * 1024, SLAB, fb + h * 8);
            }
          }
          fb ^= 16;
          if (++k5 == 5) { k5 = 0; fb ^= 48; }
        }
      }
      if (role != 2) {
        const unsigned epoch = get_epoch(misc);
        unsigned prev = 0;
#pragma unroll 1
        for (int tries = 0; tries < 20000 && prev != ~0u; tries++) {
          const unsigned r = poll_ready(role, rb, lane, epoch);
          if (r != prev) {
            asm volatile("fence.proxy.async.global;" ::: "memory");
            __syncwarp();
            if (lane == 0) asm volatile("red.release.cta.shared.or.b32 [%0], %1;" ::"r"(misc + M_RDY), "r"(r) : "memory");
            prev = r;
          } else {
            __nanosleep(100);
          }
        }
      }
    } else if (warp == 14) {
      cluster_wait();
      if (role != 2) {
        const unsigned epoch = get_epoch(misc);
        const int lb = rb * 8 + role * 4 + ct;
        mbar_wait(misc + B_RES + 16, 0);
#pragma unroll 1
        for (int i = 1; i < 5; i++) {
          if (i < ntiles) prefetch_tile(p, R.tile(i), rb, lane);
          if (i == 1) {
            mbar_wait_long(misc + B_SFREE + XSTART * 8, 0);
            wait_xn(rb, epoch);
#pragma unroll 1
            for (int kb = 0; kb < 10; kb++) {
              mbar_wait(misc + B_SFREE + kb * 8, 0);
              if (kb >= XPACE) mbar_wait(misc + B_RES + (kb - XPACE) * 8, 1);
              if (elect_one()) {
                mbar_expect_tx(misc + B_RES + kb * 8, SLAB);
                bulk_ld(sbase + kb * SLAB, g_xn + (rb * 10 + kb) * 1024, SLAB, misc + B_RES + kb * 8);
              }
            }
          } else {
            const char* src = (const char*)(i == 2 ? p.wd : i == 3 ? p.cre : p.cim);
            const int n = i == 2 ? 135 : 50;
#pragma unroll 1
            for (int k = lane; k < n; k += 32) prefetch_l2(src + (lb * n + k) * 128);
            if (i < 4) __nanosleep(2200);
          }
        }
        mbar_wait_long(misc + B_MARK, 0);
        const int nk = role ? 27 : 20;
        const uint4* abase = (role ? g_hg + (size_t)rb * 27 * 1024 : g_hs + (size_t)rb * 20 * 1024);
        unsigned ready = poll_ready(role, rb, lane, epoch);
        asm volatile("fence.proxy.async.global;" ::: "memory");
        int slot = 0, par = 0;
#pragma unroll 1
        for (int it = 0; it < nk; it++) {
          const uint32_t dst = sbase + slot * ST2, bar = misc + B_FULL2 + slot * 8;
          mbar_wait(misc + B_EMPTY2 + slot * 8, par);
          if (elect_one()) {
            mbar_expect_tx(bar, ST2);
            if (role) tma_5d_mc(dst + SLAB + rank * 10240, &tm_wd, bar, 0, it * 32 + rank * 16, ct * 5);
            else tma_5d_mc(dst + SLAB + rank * 10240, (it & 1) ? &tm_cim : &tm_cre, bar, (it >> 1) * 64, 0, ct * 10 + rank * 5);
          }
          if (!((ready >> it) & 1)) {
#pragma unroll 1
            for (int tries = 0; tries < 200000 && !((ready >> it) & 1); tries++) {
              asm volatile("ld.acquire.cta.shared.u32 %0, [%1];" : "=r"(ready) : "r"(misc + M_RDY) : "memory");
              if (!((ready >> it) & 1)) __nanosleep(40);
            }
          }
          if (elect_one()) bulk_ld(dst, abase + it * 1024, SLAB, bar);
          if (it == 4) {
            mbar_wait(misc + B_EMPTY2 + 40, 0);
            if (elect_one()) {
              mbar_expect_tx(misc + B_FULL2 + 40, 20480);
              tma_4d(sbase + 5 * ST2, &tm_xo, misc + B_FULL2 + 40, ct * 160, 0, rb * 4, 2 - 2 * role);
            }
          }
          if (++slot == NST2 - 1) { slot = 0; par ^= 1; }
        }
      }
    } else {
      const int wg = warp == 15;
      unsigned long long ticket = 0;
      if (threadIdx.x == 416) ticket = atomicAdd(&g_ticket, 1ull);
      __syncwarp();
      cluster_wait();
      if (threadIdx.x == 416) {
        asm volatile("st.shared.u32 [%0], %1;" ::"r"(misc + M_EPOCH), "r"((unsigned)(ticket / NCTA) + 1u) : "memory");
        mbar_arrive(misc + B_EPOCH);
      }
      __syncwarp();
      const unsigned epoch = get_epoch(misc);
      if (role != 2 && wg == 1) {
        mbar_wait(misc + B_XN, 0);
        if (lane == 0) {
          asm volatile("fence.acq_rel.gpu;\nred.relaxed.gpu.global.add.u32 [%0], 1;" ::"l"(g_cntX + rb * 32) : "memory");
        }
        __syncwarp();
        wait_xn(rb, epoch);
#pragma unroll
        for (int i = 0; i < 4; i++) {
          const float2 st = __ldcg(g_stats + rb * 128 + 32 * i + lane);
          asm volatile("st.shared.f32 [%0], %1;" ::"r"(misc + M_NM + (36 * i + lane) * 4), "f"(st.x) : "memory");
          asm volatile("st.shared.f32 [%0], %1;" ::"r"(misc + M_RS + (36 * i + lane) * 4), "f"(st.y) : "memory");
        }
        __syncwarp();
        if (lane == 0) {
          mbar_arrive(misc + B_STAT);
        }
      } else if (role != 2) {
        mbar_wait_long(misc + B_SFREE + 24, 0);
        const uint4* src = g_cs + (role * 4 + ct) * 128 + lane;
        uint4 a[4];
#pragma unroll 1
        for (int tries = 0; tries < 20000; tries++) {
#pragma unroll
          for (int i = 0; i < 4; i++) a[i] = ld_relaxed_v4(src + 32 * i);
          if (__all_sync(~0u, ((a[0].y ^ epoch) | (a[1].y ^ epoch) | (a[2].y ^ epoch) | (a[3].y ^ epoch)) == 0)) break;
        }
#pragma unroll
        for (int i = 0; i < 4; i++) asm volatile("st.shared.u32 [%0], %1;" ::"r"(misc + M_CS + (32 * i + lane) * 4), "r"(a[i].x) : "memory");
        __syncwarp();
        if (lane == 0) { mbar_arrive(misc + B_STAT); }
      }
      if (lane == 0) {
#pragma unroll 1
        for (int tile = wg; tile < ntiles; tile += 2) {
          mbar_wait_long(misc + B_DONE + tile * 8, 0);
          flag_set(g_flagH + (role == 2 ? rb + tile : rb) * 40 + R.tile(tile), epoch);
        }
      }
      __syncwarp();
      if (wg == 1 - role) {
        const uint4* src = reinterpret_cast<const uint4*>(g_gb) + ((rb * 4 + ct) * 2 + wg) * 32 + lane;
        uint4 b;
#pragma unroll 1
        for (int tries = 0; tries < 40000; tries++) {
          asm volatile("ld.relaxed.gpu.global.v4.u32 {%0,%1,%2,%3}, [%4];" : "=r"(b.x), "=r"(b.y), "=r"(b.z), "=r"(b.w) : "l"(src) : "memory");
          if (__all_sync(~0u, (((b.x ^ epoch) | (b.y ^ epoch) | (b.z ^ epoch) | (b.w ^ epoch)) & 1) == 0)) break;
          __nanosleep(50);
        }
        asm volatile("st.shared.v4.u32 [%0], {%1,%2,%3,%4};" ::"r"(misc + M_CS + lane * 16), "r"(b.x), "r"(b.y), "r"(b.z), "r"(b.w) : "memory");
        mbar_wait(misc + B_INOK, 0);
        __syncwarp();
#pragma unroll 1
        for (int i = 0; i < 5; i++)
          if (elect_one()) {
            mbar_expect_tx(misc + B_RES + i * 8, 4096);
            bulk_ld(sbase + role * 8192 + i * ST2, g_gx + ((rb * 4 + ct) * 2 + wg) * 1280 + i * 256, 4096, misc + B_RES + i * 8);
          }
      }
    }
  } else {
    const int wg = warp >> 2, w = warp & 3, tid = threadIdx.x & 127;
    int tile = wg;
    {
      const Role R = get_role(p);
      const int sid = R.tile(wg);
      const int ch = sid < 27 ? 0 : (sid - 27) * 64 + 16 * w + 8 * (lane & 1) + (lane >> 2);
      const uint32_t plr = ld_u16(p.lre + ch), pli = ld_u16(p.lim + ch), pld = ld_u16(p.logdt + ch);
      cluster_arrive();
      if (R.role == 2 || wg == 0) {
        cluster_wait();
      } else {
        const int t = (R.role * 4 + R.ct) * 16 + ((threadIdx.x - 128) >> 4), l16 = threadIdx.x & 15;
        uint4 xr[5];
        const uint4* xsrc = reinterpret_cast<const uint4*>(p.x + (size_t)(R.rb * 128 + t) * DM) + l16;
#pragma unroll
        for (int u = 0; u < 5; u++) xr[u] = ld_nc_v4(xsrc + 16 * u);
        float s4[4] = {0.f, 0.f, 0.f, 0.f};
#pragma unroll
        for (int u = 0; u < 5; u++) {
          s4[0] += bf_lo(xr[u].x) + bf_hi(xr[u].x); s4[1] += bf_lo(xr[u].y) + bf_hi(xr[u].y);
          s4[2] += bf_lo(xr[u].z) + bf_hi(xr[u].z); s4[3] += bf_lo(xr[u].w) + bf_hi(xr[u].w);
        }
        float sum = (s4[0] + s4[1]) + (s4[2] + s4[3]);
#pragma unroll
        for (int o = 8; o; o >>= 1) sum += __shfl_xor_sync(~0u, sum, o);
        const float mean = sum * (1.0f / DM);
        s4[0] = s4[1] = s4[2] = s4[3] = 0.f;
#pragma unroll
        for (int u = 0; u < 5; u++) {
          const uint32_t xw[4] = {xr[u].x, xr[u].y, xr[u].z, xr[u].w};
#pragma unroll
          for (int i = 0; i < 4; i++) {
            const float d0 = bf_lo(xw[i]) - mean, d1 = bf_hi(xw[i]) - mean;
            s4[i] = fmaf(d0, d0, fmaf(d1, d1, s4[i]));
          }
        }
        float var = (s4[0] + s4[1]) + (s4[2] + s4[3]);
#pragma unroll
        for (int o = 8; o; o >>= 1) var += __shfl_xor_sync(~0u, var, o);
        const float mb = round_bf16(mean);
        const float rs = __frcp_rn(round_bf16(__fsqrt_rn(round_bf16(round_bf16(var * (1.0f / DM)) + 1e-5f))));
        const NormK k = norm_consts(mb, rs);
        const int n = 8 * ((t >> 1) & 15) + 2 * (t >> 5) + (t & 1);
        uint4* dst = g_xn + (R.rb * 10 + (l16 >> 3)) * 1024 + n * 8 + ((l16 ^ n) & 7);
#pragma unroll
        for (int u = 0; u < 5; u++)
          dst[u * 2048] = make_uint4(norm2(xr[u].x, k), norm2(xr[u].y, k), norm2(xr[u].z, k), norm2(xr[u].w, k));
        if (l16 == 0) g_stats[R.rb * 128 + t] = make_float2(-mb, rs);
        cluster_wait();
        __syncwarp();
        if (lane == 0) mbar_arrive(misc + B_XN);
        if (wg == 2) {
          const int row = R.rb * 8 + (tid >> 4);
          const uint4* src = reinterpret_cast<const uint4*>((row < 64 ? p.bre : p.bim) + (size_t)((R.tile(0) - 27) * 64 + (row & 63)) * DM) + l16;
#pragma unroll
          for (int u = 0; u < 5; u++) xr[u] = ld_nc_v4(src + 16 * u);
          s4[0] = s4[1] = s4[2] = s4[3] = 0.f;
#pragma unroll
          for (int u = 0; u < 5; u++) {
            s4[0] += bf_lo(xr[u].x) + bf_hi(xr[u].x); s4[1] += bf_lo(xr[u].y) + bf_hi(xr[u].y);
            s4[2] += bf_lo(xr[u].z) + bf_hi(xr[u].z); s4[3] += bf_lo(xr[u].w) + bf_hi(xr[u].w);
          }
          sum = (s4[0] + s4[1]) + (s4[2] + s4[3]);
#pragma unroll
          for (int o = 8; o; o >>= 1) sum += __shfl_xor_sync(~0u, sum, o);
          const unsigned epoch = get_epoch(misc);
          if (l16 == 0)
            st_relaxed_v4(g_cs + (R.role * 4 + R.ct) * 128 + row, make_uint4(__float_as_uint(sum), epoch, __float_as_uint(sum), epoch));
        }
      }
      asm volatile("setmaxnreg.inc.sync.aligned.u32 160;");
      if (sid >= 27) {
        const cplx lamq = lam_bar(bf_lo(plr), bf_lo(pli), bf_lo(pld));
        const float lr = bf_lo(plr), li = bf_lo(pli), nr = lamq.r - 1.0f, den = 2.0f / (lr * lr + li * li);
        const cplx cq = {(nr * lr + lamq.i * li) * den, (lamq.i * lr - nr * li) * den};
        float acc[2][64];
        mainloop1<0, 1, 1, 1>(acc, sbase, tile, wg, tile == 0, 2, 256, lane, [] {});
        const Role Q = get_role(p);
        mbar_wait(misc + B_STAT, 0);
        epilogue_ssm(acc, lamq, cq, Q.rb, Q.tile(wg) - 27, w, lane, get_epoch(misc), p.ones, misc, wg == 0);
        __syncwarp();
        if (lane == 0) mbar_arrive(misc + B_DONE + wg * 8);
        tile += 4;
      }
    }
#pragma unroll 1
    for (;; tile += wg == 1 ? 2 : 4) {
      float acc[2][64];
      uint32_t hdst;
      auto shadow = [&] {
        const Role Q = get_role(p);
        hdst = glu_dst((Q.role == 2 ? Q.rb + tile : Q.rb) * 27 + Q.tile(tile), w, lane);
      };
      {
        const Role R = get_role(p);
        if (tile >= R.ntiles) break;
        const bool last = tile == R.ntiles - 1;
        const int nb = (0x1232 >> (4 * tile)) & 3;
        if (R.role == 2) {
          if (tile == 0)
#pragma unroll 1
            for (int kb = 0; kb < 10; kb++) mbar_wait(misc + B_RES + kb * 8, 0);
          mainloop1<1, 1, 0, 0>(acc, sbase, tile, wg, false, last ? 0 : nb, 256, lane, shadow);
        } else {
          if (tile == 1) mainloop1<1, 0, 1, 0>(acc, sbase, tile, wg, false, nb, 256, lane, shadow);
          else mainloop1<1, 0, 0, 2>(acc, sbase, tile, wg, last, last ? 4 : nb, last ? 384 : 256, lane, shadow);
        }
      }
      const Role R = get_role(p);
      if (R.role != 2 && tile >= R.ntiles - 2 && lane < 12 && (lane >= 8 || tile == R.ntiles - 2)) {
        uint32_t a;
        asm volatile("mapa.shared::cluster.u32 %0, %1, %2;" : "=r"(a) : "r"(misc + B_EMPTY2 + (lane >> 1) * 8), "r"(lane & 1));
        mbar_arrive_remote(a);
        if (tid == 0) mbar_arrive(misc + B_MARK);
      }
      epilogue_glu(acc, hdst, p.ones);
      __syncwarp();
      if (lane == 0) mbar_arrive(misc + B_DONE + tile * 8);
    }
    const Role R = get_role(p);
    const int rb = R.rb, ct = R.ct;
    const int hw = wg >> 1;
    const bool p2 = wg != R.role;
    const int g = lane >> 2, q = lane & 3, pairi = rb * 4 + ct;
    const uint32_t xe = sbase + 5 * ST2 + w * 5120 + lane * 16;
    if (R.role != 2) {
      const int fh = 1 - R.role;
      const unsigned par = get_epoch(misc) & 1;
      if (p2) {
        uint32_t wv[10][4];
        if (R.role == 1) {
          float acc[80];
          mainloop2<1, RG>(acc, sbase, hw, lane);
          wgmma_wait<0>();
          reg_fence(acc);
#pragma unroll
          for (int k = 0; k < 40; k++) {
            const int a = 16 * (k >> 3) + 4 * ((k >> 2) & 1) + 8 * ((k >> 1) & 1) + 2 * (k & 1);
            wv[k >> 2][k & 3] = pack_bf16(acc[a], acc[a + 1]);
          }
        } else {
          float acc[80];
          mainloop2<0, RS>(acc, sbase, hw, lane);
          wgmma_wait<0>();
          reg_fence(acc);
#pragma unroll
          for (int k = 0; k < 40; k++) wv[k >> 2][k & 3] = pack_bf16(acc[2 * k], acc[2 * k + 1]);
        }
        if (hw == fh) asm volatile("bar.sync 6, 128;" ::: "memory");
        else if (lane == 0) mbar_arrive(misc + B_INOK);
        if (hw == fh) {
#pragma unroll
          for (int v = 0; v < 10; v++)
            asm volatile("st.shared.v4.u32 [%0], {%1,%2,%3,%4};" ::"r"(sbase + hw * 8192 + tid * 16 + (v >> 1) * ST2 + (v & 1) * 2048),
                         "r"(wv[v][0]), "r"(wv[v][1]), "r"(wv[v][2]), "r"(wv[v][3]) : "memory");
        } else {
          uint32_t word = 0;
#pragma unroll
          for (int v = 0; v < 10; v++) {
            word = __funnelshift_r(word, wv[v][0], 1);
            word = __funnelshift_r(word, wv[v][2], 1);
            wv[v][0] = (wv[v][0] & ~1u) | par; wv[v][2] = (wv[v][2] & ~1u) | par;
          }
          uint4* dst = g_gx + (pairi * 2 + hw) * 1280 + tid;
#pragma unroll
          for (int v = 0; v < 10; v++) {
            if (v == BITPOS)
              asm volatile("st.relaxed.gpu.global.u32 [%0], %1;" ::"l"(reinterpret_cast<unsigned*>(g_gb) + (pairi * 2 + hw) * 128 + tid), "r"(word | par) : "memory");
            st_relaxed_v4(dst + v * 128, make_uint4(wv[v][0], wv[v][1], wv[v][2], wv[v][3]));
          }
        }
      } else {
      const uint2* dr = reinterpret_cast<const uint2*>(p.dskip + ct * 160) + q;
      uint2 dv[10];
      uint32_t xv[10][4];
#pragma unroll
      for (int J = 0; J < 10; J++) dv[J] = ld_nc_v2(dr + 4 * J);
      if (tid == 0) prefetch_tmap(&tm_out);
      mbar_wait(misc + B_STAT, 0);
      NormK nk[2];
#pragma unroll
      for (int half = 0; half < 2; half++) {
        const uint32_t o = (72 * (w & 1) + 16 * (1 - R.role) + 8 * (w >> 1) + g + 36 * half) * 4;
        nk[half] = norm_consts(-lds_f32(misc + M_NM + o), lds_f32(misc + M_RS + o));
      }
      mbar_wait(misc + B_FULL2 + 40, 0);
      const uint32_t xs = sbase + 5 * ST2 + (16 * w + g) * 320 + q * 8;
#pragma unroll
      for (int J = 0; J < 10; J++)
#pragma unroll
        for (int half = 0; half < 2; half++)
          asm volatile("ld.shared.v2.u32 {%0,%1}, [%2];" : "=r"(xv[J][half]), "=r"(xv[J][2 + half]) : "r"(xs + half * 2560 + J * 32) : "memory");
#pragma unroll
      for (int J = 0; J < 10; J++)
        asm volatile("st.shared.v4.u32 [%0], {%1,%2,%3,%4};" ::"r"(xe + 20480 + J * 512), "r"(hmul2(norm2(xv[J][0], nk[0]), dv[J].x)),
                     "r"(hmul2(norm2(xv[J][1], nk[1]), dv[J].x)), "r"(hmul2(norm2(xv[J][2], nk[0]), dv[J].y)),
                     "r"(hmul2(norm2(xv[J][3], nk[1]), dv[J].y)) : "memory");
      __syncwarp();
#pragma unroll
      for (int J = 0; J < 10; J++)
        asm volatile("st.shared.v4.u32 [%0], {%1,%2,%3,%4};" ::"r"(xe + J * 512), "r"(xv[J][0]), "r"(xv[J][1]), "r"(xv[J][2]), "r"(xv[J][3]) : "memory");
      }
      const int go = (q >> 1) * 128 + (tid & ~3) + 2 * (q & 1);
      const uint32_t osw = g * 128 + ((q ^ g) << 4);
      auto lds4 = [&](uint4& v, uint32_t a) {
        asm volatile("ld.shared.v4.u32 {%0,%1,%2,%3}, [%4];" : "=r"(v.x), "=r"(v.y), "=r"(v.z), "=r"(v.w) : "r"(a) : "memory");
      };
      const uint4* rsrc = g_gx + (pairi * 2 + fh) * 1280 + (fh ? go : tid);
      const uint32_t lo = fh ? 8192 + tid * 16 : go * 16, ls = fh ? 2048 : 16, ro = fh ? go * 16 : 8192 + tid * 16, rs = fh ? 16 : 2048;
      const uint32_t ba = misc + M_CS + (fh ? (tid >> 2) * 16 + (q & 1) * 8 : tid * 4), bsh = fh ? 12 + 2 * (q >> 1) : 12;
      asm volatile("bar.sync 7, 384;" ::: "memory");
#pragma unroll 1
      for (int Jp = wg; Jp < 5; Jp += 3) {
        const uint32_t ca = sbase + Jp * ST2, xa = xe + Jp * 1024;
        const uint32_t ost = sbase + (2 + (w >> 1)) * ST2 + SLAB + (w & 1) * 10240 + Jp * 2048;
        uint4 lv[2], rv[2], x[2], e[2];
#pragma unroll
        for (int i = 0; i < 2; i++) { lds4(lv[i], ca + lo + i * ls); lds4(x[i], xa + i * 512); lds4(e[i], xa + 20480 + i * 512); }
        mbar_wait(misc + B_RES + Jp * 8, 0);
        uint32_t b0, b1;
        lds4(rv[0], ca + ro); lds4(rv[1], ca + ro + rs);
        asm volatile("ld.shared.u32 %0, [%1];" : "=r"(b0) : "r"(ba) : "memory");
        asm volatile("ld.shared.u32 %0, [%1];" : "=r"(b1) : "r"(ba + fh * 4) : "memory");
#pragma unroll 1
        for (int tries = 0; tries < 20000; tries++) {
          if (__all_sync(~0u, (((rv[0].x ^ par) | (rv[0].z ^ par) | (rv[1].x ^ par) | (rv[1].z ^ par)) & 1) == 0)) break;
          rv[0] = ld_relaxed_v4(rsrc + Jp * 256); rv[1] = ld_relaxed_v4(rsrc + Jp * 256 + (fh ? 1 : 128));
        }
        b0 >>= bsh + 4 * Jp; b1 >>= bsh + 4 * Jp + 2 - 2 * fh;
        rv[0].x = (rv[0].x & ~1u) | (b0 & 1); rv[0].z = (rv[0].z & ~1u) | ((b0 >> 1) & 1);
        rv[1].x = (rv[1].x & ~1u) | (b1 & 1); rv[1].z = (rv[1].z & ~1u) | ((b1 >> 1) & 1);
        const uint4 sv[2] = {fh ? lv[0] : rv[0], fh ? lv[1] : rv[1]}, gv[2] = {fh ? rv[0] : lv[0], fh ? rv[1] : lv[1]};
#pragma unroll
        for (int J = 0; J < 2; J++) {
          const uint32_t d[4] = {J ? gv[0].z : gv[0].x, J ? gv[0].w : gv[0].y, J ? gv[1].z : gv[1].x, J ? gv[1].w : gv[1].y};
          const uint32_t sw[4] = {sv[J].x, sv[J].y, sv[J].z, sv[J].w};
          const uint32_t xw[4] = {x[J].x, x[J].y, x[J].z, x[J].w}, ew[4] = {e[J].x, e[J].y, e[J].z, e[J].w};
          float o[8];
#pragma unroll
          for (int k = 0; k < 4; k++) {
            o[2 * k] = fmaf(bf_lo(sw[k]) + bf_lo(ew[k]), silu(bf_lo(d[k])), bf_lo(xw[k]));
            o[2 * k + 1] = fmaf(bf_hi(sw[k]) + bf_hi(ew[k]), silu(bf_hi(d[k])), bf_hi(xw[k]));
          }
#pragma unroll
          for (int half = 0; half < 2; half++)
            asm volatile("st.shared.v4.f32 [%0], {%1,%2,%3,%4};" ::"r"(ost + (osw ^ (J * 64)) + half * 1024), "f"(o[2 * half]),
                         "f"(o[2 * half + 1]), "f"(o[4 + 2 * half]), "f"(o[5 + 2 * half]) : "memory");
        }
        asm volatile("fence.proxy.async.shared::cta;" ::: "memory");
        __syncwarp();
        if (elect_one())
          asm volatile("cp.async.bulk.tensor.4d.global.shared::cta.bulk_group [%0, {%2, %3, %4, %5}], [%1];\ncp.async.bulk.commit_group;"
                       ::"l"(&tm_out), "r"(ost), "r"(ct * 160 + 32 * Jp), "r"(0), "r"(rb * 4 + 2 * (w & 1)), "r"(2 * fh + (w >> 1)) : "memory");
      }
      asm volatile("cp.async.bulk.wait_group.read 0;" ::: "memory");
    }
  }
}

typedef CUresult (*EncodeFn)(CUtensorMap*, CUtensorMapDataType, cuuint32_t, void*, const cuuint64_t*, const cuuint64_t*,
                             const cuuint32_t*, const cuuint32_t*, CUtensorMapInterleave, CUtensorMapSwizzle,
                             CUtensorMapL2promotion, CUtensorMapFloatOOBfill);

void make_map(EncodeFn enc, CUtensorMap* m, const void* ptr, int rank, const cuuint64_t* dims, const cuuint64_t* strides,
              const cuuint32_t* box, CUtensorMapSwizzle swz) {
  cuuint32_t es[5] = {1, 1, 1, 1, 1};
  enc(m, CU_TENSOR_MAP_DATA_TYPE_BFLOAT16, rank, const_cast<void*>(ptr), dims, strides, box, es,
      CU_TENSOR_MAP_INTERLEAVE_NONE, swz, CU_TENSOR_MAP_L2_PROMOTION_L2_128B, CU_TENSOR_MAP_FLOAT_OOB_FILL_NONE);
}
void make_map_2d(EncodeFn enc, CUtensorMap* m, const void* ptr, int cols, int rows, int boxc, int boxr) {
  cuuint64_t d[2] = {(cuuint64_t)cols, (cuuint64_t)rows}, s[1] = {(cuuint64_t)cols * 2};
  cuuint32_t b[2] = {(cuuint32_t)boxc, (cuuint32_t)boxr};
  make_map(enc, m, ptr, 2, d, s, b, CU_TENSOR_MAP_SWIZZLE_128B);
}

}

extern "C" void kernel_launch(void* const* d_in, const int* in_sizes, int n_in, void* d_out, int out_size) {
  (void)in_sizes; (void)n_in; (void)out_size;
  void* fn = nullptr;
  cudaDriverEntryPointQueryResult qs;
  cudaGetDriverEntryPoint("cuTensorMapEncodeTiled", &fn, cudaEnableDefault, &qs);
  EncodeFn enc = (EncodeFn)fn;

  CUtensorMap tm_x, tm_bre, tm_bim, tm_wg, tm_wu, tm_xo, tm_wd, tm_cre, tm_cim, tm_out;
  {
    cuuint64_t d[4] = {DM, 2, 64, 16}, s[3] = {DM * 2, 32 * DM * 2, 2 * DM * 2};
    cuuint32_t b[4] = {64, 2, 4, 16};
    make_map(enc, &tm_x, d_in[0], 4, d, s, b, CU_TENSOR_MAP_SWIZZLE_128B);
  }
  make_map_2d(enc, &tm_bre, d_in[3], DM, DM, 64, 64);
  make_map_2d(enc, &tm_bim, d_in[4], DM, DM, 64, 64);
  make_map_2d(enc, &tm_wg, d_in[10], DF, DM, 64, 64);
  make_map_2d(enc, &tm_wu, d_in[11], DF, DM, 64, 64);
  {
    cuuint64_t d[4] = {DM, 8, 64, 4}, s[3] = {DM * 2, 32 * DM * 2, 8 * DM * 2};
    cuuint32_t b[4] = {160, 8, 4, 2};
    make_map(enc, &tm_xo, d_in[0], 4, d, s, b, CU_TENSOR_MAP_SWIZZLE_NONE);
  }
  {
    cuuint64_t d[5] = {32, 2, 4, DF / 2 - 12, DM / 32}, s[4] = {DM * 2, 8 * DM * 2, 2 * DM * 2, 64};
    cuuint32_t b[5] = {32, 2, 4, 4, 5};
    make_map(enc, &tm_wd, d_in[12], 5, d, s, b, CU_TENSOR_MAP_SWIZZLE_64B);
  }
  {
    cuuint64_t d[5] = {DM, 2, 4, 2, DM / 16}, s[4] = {DM * 2, 4 * DM * 2, 2 * DM * 2, 16 * DM * 2};
    cuuint32_t b[5] = {64, 2, 4, 2, 5};
    make_map(enc, &tm_cre, d_in[5], 5, d, s, b, CU_TENSOR_MAP_SWIZZLE_128B);
    make_map(enc, &tm_cim, d_in[6], 5, d, s, b, CU_TENSOR_MAP_SWIZZLE_128B);
  }
  {
    cuuint64_t d[4] = {DM, 8, 64, 4}, s[3] = {DM * 4, 32 * DM * 4, 8 * DM * 4};
    cuuint32_t b[4] = {32, 8, 2, 1}, es[4] = {1, 1, 1, 1};
    enc(&tm_out, CU_TENSOR_MAP_DATA_TYPE_FLOAT32, 4, d_out, d, s, b, es, CU_TENSOR_MAP_INTERLEAVE_NONE, CU_TENSOR_MAP_SWIZZLE_128B,
        CU_TENSOR_MAP_L2_PROMOTION_NONE, CU_TENSOR_MAP_FLOAT_OOB_FILL_NONE);
  }
  Params p;
  p.x = (const bf16*)d_in[0]; p.lre = (const bf16*)d_in[1]; p.lim = (const bf16*)d_in[2];
  p.logdt = (const bf16*)d_in[7]; p.dskip = (const bf16*)d_in[8];
  p.bre = (const bf16*)d_in[3]; p.bim = (const bf16*)d_in[4]; p.wg = (const bf16*)d_in[10]; p.wu = (const bf16*)d_in[11];
  p.cre = (const bf16*)d_in[5]; p.cim = (const bf16*)d_in[6]; p.wd = (const bf16*)d_in[12];
  p.out = (float*)d_out;
  p.ones = ~0u;
  static const unsigned char map[66] = {62, 63, 64, 65, 56, 0, 8, 16, 24, 32, 40, 48, 57, 1, 9, 17, 25, 33, 41, 49, 58, 2,
                                        10, 18, 26, 34, 42, 50, 59, 3, 11, 19, 27, 35, 43, 51, 4, 12, 20, 28, 36, 44, 52, 5,
                                        13, 21, 29, 37, 45, 53, 6, 14, 22, 30, 38, 46, 54, 7, 15, 23, 31, 39, 47, 55, 60, 61};
  for (int i = 0; i < 66; i++) p.map[i] = map[i];

  cudaFuncSetAttribute(fused_kernel, cudaFuncAttributeMaxDynamicSharedMemorySize, SMEM_BYTES);
  fused_kernel<<<NCTA, 512, SMEM_BYTES, cudaStreamPerThread>>>(tm_x, tm_bre, tm_bim, tm_wg, tm_wu, tm_xo, tm_wd, tm_cre, tm_cim, tm_out, p);
}
```
